```python
import torch

def _softmax(x, axis=-1):
    return torch.softmax(x, dim=axis)
def _gelu(x):
    return torch.nn.functional.gelu(x, approximate="tanh")
def _silu(x):
    return torch.nn.functional.silu(x)
def _sigmoid(x):
    return torch.sigmoid(x)
def _layernorm(x, axis=-1, eps=1e-5):
    m = x.mean(dim=axis, keepdim=True)
    v = x.var(dim=axis, keepdim=True, unbiased=False)
    return (x - m) / torch.sqrt(v + eps)
def _scatter_add(tgt, idx, src, axis=0):
    return tgt.clone().index_add_(axis, idx, src)
def _segment_sum(src, seg, n):
    out = torch.zeros((n,) + src.shape[1:], dtype=src.dtype)
    return out.index_add_(0, seg, src)
def _pad(x, pw):
    flat = tuple(v for pair in reversed(pw) for v in pair)
    return torch.nn.functional.pad(x, flat)

kernel_name = 'recurrent_scan__softmax_full_mha__glu_gated_reglu__prompt'

def setup_inputs():

    _w = (lambda a: (lambda t: t.to(torch.bfloat16) if t.is_floating_point() else t)(torch.as_tensor(a)))
    def _A_setup():
        B, S, D = 1, 2048, 576
        return {
            "x": _w((lambda *s: torch.randn(*s, dtype=torch.bfloat16) * 0.05)(B, S, D)),
            "wqkv": _w((lambda *s: torch.randn(*s, dtype=torch.bfloat16) * 0.2)(D, 3 * D)),
            "wo": _w((lambda *s: torch.randn(*s, dtype=torch.bfloat16) * 0.2)(D, D)),
        }
    _A_in = _A_setup()

    def _B_setup():
        B, S, D, F = 1, 2048, 576, 4608
        return {
            "x": _w((lambda *s: torch.randn(*s, dtype=torch.bfloat16) * 0.05)(B, S, D)),
            "W_gate": _w((lambda *s: torch.randn(*s, dtype=torch.bfloat16) * 0.1)(D, F) * (2.0 / D) ** 0.5),
            "W_up": _w((lambda *s: torch.randn(*s, dtype=torch.bfloat16) * 0.1)(D, F) * (2.0 / D) ** 0.5),
            "W_down": _w((lambda *s: torch.randn(*s, dtype=torch.bfloat16) * 0.1)(F, D) * (1.0 / F) ** 0.5),
        }
    _B_in = _B_setup()

    return {
        "A_x": _A_in["x"],
        "A_wqkv": _A_in["wqkv"],
        "A_wo": _A_in["wo"],
        "B_x": _B_in["x"],
        "B_W_gate": _B_in["W_gate"],
        "B_W_up": _B_in["W_up"],
        "B_W_down": _B_in["W_down"],
    }

def reference(A_x, A_wqkv, A_wo, B_x, B_W_gate, B_W_up, B_W_down):
    def _A_ref(x, wqkv, wo):
        B, S, D = x.shape
        H = 32; Dh = D // H
        qkv = (lambda x, *d: x.permute(*d))((x @ wqkv).reshape(B, S, 3, H, Dh), 2, 0, 3, 1, 4)
        q, k, v = qkv[0], qkv[1], qkv[2]
        scale = Dh ** -0.5
        scores = torch.einsum("bhqd,bhkd->bhqk", q, k) * scale
        p = _softmax(scores, axis=-1)
        o = torch.einsum("bhqk,bhkd->bhqd", p, v)
        return (lambda x, *d: x.permute(*d))(o, 0, 2, 1, 3).reshape(B, S, D) @ wo

    def _B_ref(x, W_gate, W_up, W_down):
        gate = torch.einsum("bsd,df->bsf", x, W_gate)
        up = torch.einsum("bsd,df->bsf", x, W_up)
        gate = gate * (lambda x, dt: x.to(dt))(gate > 0, gate.dtype)
        h = gate * up
        return torch.einsum("bsf,fd->bsd", h, W_down)

    x = A_x
    xn = _layernorm(x, axis=-1)
    s = _A_ref(xn, A_wqkv, A_wo)
    g = _silu(_B_ref(xn, B_W_gate, B_W_up, B_W_down))
    return x + s * g
```

```cpp
#include <cuda_runtime.h>
#include <cuda_bf16.h>
#include <cuda.h>
#include <stdint.h>

namespace {

constexpr int S_LEN = 2048, DM = 576, FF = 4608;
#define NPRE 2
constexpr float QSCALE = 0.23570226039551584f * 1.4426950408889634f;
constexpr uint32_t EMPTY = 0xFFFFFFFFu;
constexpr float MOFF = 90.0f;

constexpr uint32_t SM_XN = 0;
constexpr uint32_t SM_W = 147456;
constexpr uint32_t SM_XT = SM_XN;
constexpr uint32_t SM_KV = SM_W + 65536;
constexpr uint32_t SM_BAR = SM_KV + 18432;
constexpr uint32_t B_WFULL = 0, B_WEMPTY = 32, B_KEMPTY = 96, B_LEFT = 200,
                   B_KVDONE = 208, B_OEARLY = 224, B_FFNDONE = 232, B_LATE = 240, B_FFNOK = 256, B_ZOK = 272, B_XS = 280, B_DONE = 416, B_STG = 424, B_QW = 432, B_EARLYOK = 64, B_XD = 72, B_LEFT2 = 80, B_KV0 = 216, B_X = 128  , B_HD = 440  ,
                   B_BAD = 288;
constexpr uint32_t SM_TOTAL = SM_BAR + 512;

struct __align__(1024) Scratch {
  uint8_t k[32 * 2048 * 48];
  uint8_t v[32 * 2048 * 48];
  uint8_t h[128 * 9 * 16384];
  float down[S_LEN * DM];
  uint32_t qb[128 * 8 * 4 * 192];
  uint8_t oe[16 * 6 * 16384];
  uint32_t o[128 * 8 * 128];
  uint32_t ol[128 * 8 * 64];
  uint32_t epoch[128], cnt_kv[8 * 32], cnt_kv0[64 * 32], cnt_zero[16 * 32], cnt_early[16 * 32], cnt_ffn[16 * 32];
};
__device__ __align__(1024) Scratch g_scratch;
#define TS(i)
#define TP(i)
#define TQ(i)
#define TEXTRA 0

#define TH(i)
#define TI()
struct Maps { CUtensorMap qkv, wg, wu, wd, woe, woa, wob, x; };
struct Ptrs { const uint8_t *x, *wqkv, *wo, *wg, *wu, *wd; uint8_t* out; Scratch* s; int one; };

__device__ __forceinline__ void mma_rs24_t(float (&d)[12], uint32_t a0, uint32_t a1, uint32_t a2, uint32_t a3, uint64_t db, int sd) {
  asm volatile("{\n.reg .pred p;\nsetp.ne.b32 p, %17, 0;\n"
    "wgmma.mma_async.sync.aligned.m64n24k16.f32.bf16.bf16 {%0, %1, %2, %3, %4, %5, %6, %7, %8, %9, %10, %11}, "
    "{%12, %13, %14, %15}, %16, p, 1, 1, 1;\n}\n"
    : "+f"(d[0]), "+f"(d[1]), "+f"(d[2]), "+f"(d[3]), "+f"(d[4]), "+f"(d[5]), "+f"(d[6]), "+f"(d[7]), "+f"(d[8]), "+f"(d[9]), "+f"(d[10]), "+f"(d[11])
    : "r"(a0), "r"(a1), "r"(a2), "r"(a3), "l"(db), "r"(sd));
}
__device__ __forceinline__ void mma_rs64_n(float (&d)[32], uint32_t a0, uint32_t a1, uint32_t a2, uint32_t a3, uint64_t db, int sd) {
  asm volatile("{\n.reg .pred p;\nsetp.ne.b32 p, %37, 0;\n"
    "wgmma.mma_async.sync.aligned.m64n64k16.f32.bf16.bf16 {%0, %1, %2, %3, %4, %5, %6, %7, %8, %9, %10, %11, %12, %13, %14, %15, %16, %17, %18, %19, %20, %21, %22, %23, %24, %25, %26, %27, %28, %29, %30, %31}, "
    "{%32, %33, %34, %35}, %36, p, 1, 1, 0;\n}\n"
    : "+f"(d[0]), "+f"(d[1]), "+f"(d[2]), "+f"(d[3]), "+f"(d[4]), "+f"(d[5]), "+f"(d[6]), "+f"(d[7]), "+f"(d[8]), "+f"(d[9]), "+f"(d[10]), "+f"(d[11]), "+f"(d[12]), "+f"(d[13]), "+f"(d[14]), "+f"(d[15]), "+f"(d[16]), "+f"(d[17]), "+f"(d[18]), "+f"(d[19]), "+f"(d[20]), "+f"(d[21]), "+f"(d[22]), "+f"(d[23]), "+f"(d[24]), "+f"(d[25]), "+f"(d[26]), "+f"(d[27]), "+f"(d[28]), "+f"(d[29]), "+f"(d[30]), "+f"(d[31])
    : "r"(a0), "r"(a1), "r"(a2), "r"(a3), "l"(db), "r"(sd));
}
__device__ __forceinline__ void mma_ss128_t(float (&d)[64], uint64_t da, uint64_t db, int sd) {
  asm volatile("{\n.reg .pred p;\nsetp.ne.b32 p, %66, 0;\n"
    "wgmma.mma_async.sync.aligned.m64n128k16.f32.bf16.bf16 {%0, %1, %2, %3, %4, %5, %6, %7, %8, %9, %10, %11, %12, %13, %14, %15, %16, %17, %18, %19, %20, %21, %22, %23, %24, %25, %26, %27, %28, %29, %30, %31, %32, %33, %34, %35, %36, %37, %38, %39, %40, %41, %42, %43, %44, %45, %46, %47, %48, %49, %50, %51, %52, %53, %54, %55, %56, %57, %58, %59, %60, %61, %62, %63}, "
    "%64, %65, p, 1, 1, 0, 1;\n}\n"
    : "+f"(d[0]), "+f"(d[1]), "+f"(d[2]), "+f"(d[3]), "+f"(d[4]), "+f"(d[5]), "+f"(d[6]), "+f"(d[7]), "+f"(d[8]), "+f"(d[9]), "+f"(d[10]), "+f"(d[11]), "+f"(d[12]), "+f"(d[13]), "+f"(d[14]), "+f"(d[15]), "+f"(d[16]), "+f"(d[17]), "+f"(d[18]), "+f"(d[19]), "+f"(d[20]), "+f"(d[21]), "+f"(d[22]), "+f"(d[23]), "+f"(d[24]), "+f"(d[25]), "+f"(d[26]), "+f"(d[27]), "+f"(d[28]), "+f"(d[29]), "+f"(d[30]), "+f"(d[31]), "+f"(d[32]), "+f"(d[33]), "+f"(d[34]), "+f"(d[35]), "+f"(d[36]), "+f"(d[37]), "+f"(d[38]), "+f"(d[39]), "+f"(d[40]), "+f"(d[41]), "+f"(d[42]), "+f"(d[43]), "+f"(d[44]), "+f"(d[45]), "+f"(d[46]), "+f"(d[47]), "+f"(d[48]), "+f"(d[49]), "+f"(d[50]), "+f"(d[51]), "+f"(d[52]), "+f"(d[53]), "+f"(d[54]), "+f"(d[55]), "+f"(d[56]), "+f"(d[57]), "+f"(d[58]), "+f"(d[59]), "+f"(d[60]), "+f"(d[61]), "+f"(d[62]), "+f"(d[63])
    : "l"(da), "l"(db), "r"(sd));
}
__device__ __forceinline__ void mma_ss112_t(float (&d)[64], uint64_t da, uint64_t db, int sd) {
  asm volatile("{\n.reg .pred p;\nsetp.ne.b32 p, %58, 0;\n"
    "wgmma.mma_async.sync.aligned.m64n112k16.f32.bf16.bf16 {%0, %1, %2, %3, %4, %5, %6, %7, %8, %9, %10, %11, %12, %13, %14, %15, %16, %17, %18, %19, %20, %21, %22, %23, %24, %25, %26, %27, %28, %29, %30, %31, %32, %33, %34, %35, %36, %37, %38, %39, %40, %41, %42, %43, %44, %45, %46, %47, %48, %49, %50, %51, %52, %53, %54, %55}, "
    "%56, %57, p, 1, 1, 0, 1;\n}\n"
    : "+f"(d[0]), "+f"(d[1]), "+f"(d[2]), "+f"(d[3]), "+f"(d[4]), "+f"(d[5]), "+f"(d[6]), "+f"(d[7]), "+f"(d[8]), "+f"(d[9]), "+f"(d[10]), "+f"(d[11]), "+f"(d[12]), "+f"(d[13]), "+f"(d[14]), "+f"(d[15]), "+f"(d[16]), "+f"(d[17]), "+f"(d[18]), "+f"(d[19]), "+f"(d[20]), "+f"(d[21]), "+f"(d[22]), "+f"(d[23]), "+f"(d[24]), "+f"(d[25]), "+f"(d[26]), "+f"(d[27]), "+f"(d[28]), "+f"(d[29]), "+f"(d[30]), "+f"(d[31]), "+f"(d[32]), "+f"(d[33]), "+f"(d[34]), "+f"(d[35]), "+f"(d[36]), "+f"(d[37]), "+f"(d[38]), "+f"(d[39]), "+f"(d[40]), "+f"(d[41]), "+f"(d[42]), "+f"(d[43]), "+f"(d[44]), "+f"(d[45]), "+f"(d[46]), "+f"(d[47]), "+f"(d[48]), "+f"(d[49]), "+f"(d[50]), "+f"(d[51]), "+f"(d[52]), "+f"(d[53]), "+f"(d[54]), "+f"(d[55])
    : "l"(da), "l"(db), "r"(sd));
}
__device__ __forceinline__ void mma_rs72w_t(float (&d)[64], uint32_t a0, uint32_t a1, uint32_t a2, uint32_t a3, uint64_t db, int sd) {
  asm volatile("{\n.reg .pred p;\nsetp.ne.b32 p, %41, 0;\n"
    "wgmma.mma_async.sync.aligned.m64n72k16.f32.bf16.bf16 {%0, %1, %2, %3, %4, %5, %6, %7, %8, %9, %10, %11, %12, %13, %14, %15, %16, %17, %18, %19, %20, %21, %22, %23, %24, %25, %26, %27, %28, %29, %30, %31, %32, %33, %34, %35}, "
    "{%36, %37, %38, %39}, %40, p, 1, 1, 1;\n}\n"
    : "+f"(d[0]), "+f"(d[1]), "+f"(d[2]), "+f"(d[3]), "+f"(d[4]), "+f"(d[5]), "+f"(d[6]), "+f"(d[7]), "+f"(d[8]), "+f"(d[9]), "+f"(d[10]), "+f"(d[11]), "+f"(d[12]), "+f"(d[13]), "+f"(d[14]), "+f"(d[15]), "+f"(d[16]), "+f"(d[17]), "+f"(d[18]), "+f"(d[19]), "+f"(d[20]), "+f"(d[21]), "+f"(d[22]), "+f"(d[23]), "+f"(d[24]), "+f"(d[25]), "+f"(d[26]), "+f"(d[27]), "+f"(d[28]), "+f"(d[29]), "+f"(d[30]), "+f"(d[31]), "+f"(d[32]), "+f"(d[33]), "+f"(d[34]), "+f"(d[35])
    : "r"(a0), "r"(a1), "r"(a2), "r"(a3), "l"(db), "r"(sd));
}
__device__ __forceinline__ void mma_ss24_t(float (&d)[12], uint64_t da, uint64_t db, int sd) {
  asm volatile("{\n.reg .pred p;\nsetp.ne.b32 p, %14, 0;\n"
    "wgmma.mma_async.sync.aligned.m64n24k16.f32.bf16.bf16 {%0, %1, %2, %3, %4, %5, %6, %7, %8, %9, %10, %11}, "
    "%12, %13, p, 1, 1, 0, 1;\n}\n"
    : "+f"(d[0]), "+f"(d[1]), "+f"(d[2]), "+f"(d[3]), "+f"(d[4]), "+f"(d[5]), "+f"(d[6]), "+f"(d[7]), "+f"(d[8]), "+f"(d[9]), "+f"(d[10]), "+f"(d[11])
    : "l"(da), "l"(db), "r"(sd));
}
__device__ __forceinline__ void mma_rs64_t(float (&d)[64], uint32_t a0, uint32_t a1, uint32_t a2, uint32_t a3, uint64_t db, int sd) {
  asm volatile("{\n.reg .pred p;\nsetp.ne.b32 p, %37, 0;\n"
    "wgmma.mma_async.sync.aligned.m64n64k16.f32.bf16.bf16 {%0, %1, %2, %3, %4, %5, %6, %7, %8, %9, %10, %11, %12, %13, %14, %15, %16, %17, %18, %19, %20, %21, %22, %23, %24, %25, %26, %27, %28, %29, %30, %31}, "
    "{%32, %33, %34, %35}, %36, p, 1, 1, 1;\n}\n"
    : "+f"(d[0]), "+f"(d[1]), "+f"(d[2]), "+f"(d[3]), "+f"(d[4]), "+f"(d[5]), "+f"(d[6]), "+f"(d[7]), "+f"(d[8]), "+f"(d[9]), "+f"(d[10]), "+f"(d[11]), "+f"(d[12]), "+f"(d[13]), "+f"(d[14]), "+f"(d[15]), "+f"(d[16]), "+f"(d[17]), "+f"(d[18]), "+f"(d[19]), "+f"(d[20]), "+f"(d[21]), "+f"(d[22]), "+f"(d[23]), "+f"(d[24]), "+f"(d[25]), "+f"(d[26]), "+f"(d[27]), "+f"(d[28]), "+f"(d[29]), "+f"(d[30]), "+f"(d[31])
    : "r"(a0), "r"(a1), "r"(a2), "r"(a3), "l"(db), "r"(sd));
}
__device__ __forceinline__ void mma_ss64_t(float (&d)[64], uint64_t da, uint64_t db, int sd) {
  asm volatile("{\n.reg .pred p;\nsetp.ne.b32 p, %34, 0;\n"
    "wgmma.mma_async.sync.aligned.m64n64k16.f32.bf16.bf16 {%0, %1, %2, %3, %4, %5, %6, %7, %8, %9, %10, %11, %12, %13, %14, %15, %16, %17, %18, %19, %20, %21, %22, %23, %24, %25, %26, %27, %28, %29, %30, %31}, "
    "%32, %33, p, 1, 1, 0, 1;\n}\n"
    : "+f"(d[0]), "+f"(d[1]), "+f"(d[2]), "+f"(d[3]), "+f"(d[4]), "+f"(d[5]), "+f"(d[6]), "+f"(d[7]), "+f"(d[8]), "+f"(d[9]), "+f"(d[10]), "+f"(d[11]), "+f"(d[12]), "+f"(d[13]), "+f"(d[14]), "+f"(d[15]), "+f"(d[16]), "+f"(d[17]), "+f"(d[18]), "+f"(d[19]), "+f"(d[20]), "+f"(d[21]), "+f"(d[22]), "+f"(d[23]), "+f"(d[24]), "+f"(d[25]), "+f"(d[26]), "+f"(d[27]), "+f"(d[28]), "+f"(d[29]), "+f"(d[30]), "+f"(d[31])
    : "l"(da), "l"(db), "r"(sd));
}
__device__ __forceinline__ void mma_rs128_t(float (&d)[64], uint32_t a0, uint32_t a1, uint32_t a2, uint32_t a3, uint64_t db, int sd) {
  asm volatile("{\n.reg .pred p;\nsetp.ne.b32 p, %69, 0;\n"
    "wgmma.mma_async.sync.aligned.m64n128k16.f32.bf16.bf16 {%0, %1, %2, %3, %4, %5, %6, %7, %8, %9, %10, %11, %12, %13, %14, %15, %16, %17, %18, %19, %20, %21, %22, %23, %24, %25, %26, %27, %28, %29, %30, %31, %32, %33, %34, %35, %36, %37, %38, %39, %40, %41, %42, %43, %44, %45, %46, %47, %48, %49, %50, %51, %52, %53, %54, %55, %56, %57, %58, %59, %60, %61, %62, %63}, "
    "{%64, %65, %66, %67}, %68, p, 1, 1, 1;\n}\n"
    : "+f"(d[0]), "+f"(d[1]), "+f"(d[2]), "+f"(d[3]), "+f"(d[4]), "+f"(d[5]), "+f"(d[6]), "+f"(d[7]), "+f"(d[8]), "+f"(d[9]), "+f"(d[10]), "+f"(d[11]), "+f"(d[12]), "+f"(d[13]), "+f"(d[14]), "+f"(d[15]), "+f"(d[16]), "+f"(d[17]), "+f"(d[18]), "+f"(d[19]), "+f"(d[20]), "+f"(d[21]), "+f"(d[22]), "+f"(d[23]), "+f"(d[24]), "+f"(d[25]), "+f"(d[26]), "+f"(d[27]), "+f"(d[28]), "+f"(d[29]), "+f"(d[30]), "+f"(d[31]), "+f"(d[32]), "+f"(d[33]), "+f"(d[34]), "+f"(d[35]), "+f"(d[36]), "+f"(d[37]), "+f"(d[38]), "+f"(d[39]), "+f"(d[40]), "+f"(d[41]), "+f"(d[42]), "+f"(d[43]), "+f"(d[44]), "+f"(d[45]), "+f"(d[46]), "+f"(d[47]), "+f"(d[48]), "+f"(d[49]), "+f"(d[50]), "+f"(d[51]), "+f"(d[52]), "+f"(d[53]), "+f"(d[54]), "+f"(d[55]), "+f"(d[56]), "+f"(d[57]), "+f"(d[58]), "+f"(d[59]), "+f"(d[60]), "+f"(d[61]), "+f"(d[62]), "+f"(d[63])
    : "r"(a0), "r"(a1), "r"(a2), "r"(a3), "l"(db), "r"(sd));
}

#define WG_FENCE() asm volatile("wgmma.fence.sync.aligned;" ::: "memory")
#define WG_COMMIT() asm volatile("wgmma.commit_group.sync.aligned;" ::: "memory")
#define WG_WAIT(n) asm volatile("wgmma.wait_group.sync.aligned %0;" ::"n"(n) : "memory")

template <int N> __device__ __forceinline__ void keep(float (&d)[N]) {
#pragma unroll
  for (int i = 0; i < N; i++) asm volatile("" : "+f"(d[i])::"memory");
}
__device__ __forceinline__ uint64_t mkd(uint32_t lo, uint32_t hi) { return ((uint64_t)hi << 32) | lo; }
constexpr uint32_t HI_SW128 = 0x40000040u;

__device__ __forceinline__ float ex2(float x) { float y; asm("ex2.approx.ftz.f32 %0, %1;" : "=f"(y) : "f"(x)); return y; }
__device__ __forceinline__ float rcp(float x) { float y; asm("rcp.approx.ftz.f32 %0, %1;" : "=f"(y) : "f"(x)); return y; }
__device__ __forceinline__ float fsqrt(float x) { float y; asm("sqrt.approx.ftz.f32 %0, %1;" : "=f"(y) : "f"(x)); return y; }
__device__ __forceinline__ uint32_t pack(float lo, float hi) { uint32_t r; asm("cvt.rn.bf16x2.f32 %0, %1, %2;" : "=r"(r) : "f"(hi), "f"(lo)); return r; }
__device__ __forceinline__ uint32_t pack_relu(float lo, float hi) { uint32_t r; asm("cvt.rn.relu.bf16x2.f32 %0, %1, %2;" : "=r"(r) : "f"(hi), "f"(lo)); return r; }
__device__ __forceinline__ uint32_t hmul2(uint32_t a, uint32_t b) { uint32_t r; asm("mul.rn.bf16x2 %0, %1, %2;" : "=r"(r) : "r"(a), "r"(b)); return r; }
__device__ __forceinline__ uint32_t hadd2(uint32_t a, uint32_t b) { uint32_t r; asm("add.rn.bf16x2 %0, %1, %2;" : "=r"(r) : "r"(a), "r"(b)); return r; }
__device__ __forceinline__ uint32_t hsub2(uint32_t a, uint32_t b) { uint32_t r; asm("sub.rn.bf16x2 %0, %1, %2;" : "=r"(r) : "r"(a), "r"(b)); return r; }
__device__ __forceinline__ uint32_t hfma2(uint32_t a, uint32_t b, uint32_t c) { uint32_t r; asm("fma.rn.bf16x2 %0, %1, %2, %3;" : "=r"(r) : "r"(a), "r"(b), "r"(c)); return r; }
__device__ __forceinline__ float blo(uint32_t u) { return __uint_as_float(u << 16); }
__device__ __forceinline__ float bhi(uint32_t u) { return __uint_as_float(u & 0xFFFF0000u); }
__device__ __forceinline__ float bround(float x) { return blo(pack(x, 0.f)); }

__device__ __forceinline__ bool mbar_test(uint32_t bar, uint32_t parity) {
  uint32_t ok;
  asm volatile("{\n.reg .pred p;\nmbarrier.test_wait.parity.shared::cta.b64 p, [%1], %2;\nselp.u32 %0, 1, 0, p;\n}\n" : "=r"(ok) : "r"(bar), "r"(parity) : "memory");
  return ok != 0;
}
__device__ __forceinline__ void pf_line(const void* p) { asm volatile("prefetch.global.L2 [%0];" ::"l"(p) : "memory"); }
__device__ __forceinline__ void stg4(void* p, uint32_t a, uint32_t b, uint32_t c, uint32_t d) { asm volatile("st.global.v4.b32 [%0], {%1,%2,%3,%4};" ::"l"(p), "r"(a), "r"(b), "r"(c), "r"(d) : "memory"); }
__device__ __forceinline__ void stg2(void* p, uint32_t a, uint32_t b) { asm volatile("st.global.v2.b32 [%0], {%1,%2};" ::"l"(p), "r"(a), "r"(b) : "memory"); }
__device__ __forceinline__ void mbar_wait(uint32_t bar, uint32_t parity) {
  asm volatile("{\n.reg .pred p;\nLOOP_%=:\nmbarrier.try_wait.parity.shared::cta.b64 p, [%0], %1;\n@!p bra LOOP_%=;\n}\n" ::"r"(bar), "r"(parity) : "memory");
}
__device__ __forceinline__ void mbar_sleep(uint32_t bar, uint32_t parity) {
  asm volatile("{\n.reg .pred p;\nLOOP_%=:\nmbarrier.try_wait.parity.shared::cta.b64 p, [%0], %1, 20000;\n@!p bra LOOP_%=;\n}\n" ::"r"(bar), "r"(parity) : "memory");
}
__device__ __forceinline__ void mbar_guard(uint32_t bar) {
  asm volatile("{\n.reg .pred p;\n.reg .u64 t0, t1;\nmov.u64 t0, %%globaltimer;\n"
               "LOOP_%=:\nmbarrier.try_wait.parity.shared::cta.b64 p, [%0], 0, 1000000;\n@p bra DONE_%=;\n"
               "mov.u64 t1, %%globaltimer;\nsub.u64 t1, t1, t0;\nsetp.lt.u64 p, t1, 4000000000;\n@p bra LOOP_%=;\ntrap;\nDONE_%=:\n}\n" ::"r"(bar) : "memory");
}
__device__ __forceinline__ bool elect() {
  uint32_t ok;
  asm volatile("{\n.reg .pred p;\nelect.sync _|p, 0xFFFFFFFF;\nselp.u32 %0, 1, 0, p;\n}\n" : "=r"(ok));
  return ok != 0;
}
__device__ __forceinline__ void mbar_arrive(uint32_t a) { asm volatile("mbarrier.arrive.shared::cta.b64 _, [%0];" ::"r"(a) : "memory"); }
__device__ __forceinline__ void l2_prefetch(const void* p, uint32_t bytes) { asm volatile("cp.async.bulk.prefetch.L2.global [%0], %1;" ::"l"(p), "r"(bytes) : "memory"); }
__device__ __forceinline__ void mbar_init(uint32_t bar, uint32_t cnt) { asm volatile("mbarrier.init.shared::cta.b64 [%0], %1;" ::"r"(bar), "r"(cnt) : "memory"); }
__device__ __forceinline__ void mbar_expect(uint32_t bar, uint32_t bytes) { asm volatile("mbarrier.arrive.expect_tx.shared::cta.b64 _, [%0], %1;" ::"r"(bar), "r"(bytes) : "memory"); }
__device__ __forceinline__ void mbar_arrive_cl(uint32_t a) { asm volatile("mbarrier.arrive.shared::cluster.b64 _, [%0];" ::"r"(a) : "memory"); }

__device__ __forceinline__ void tma2(uint32_t dst, const CUtensorMap* m, uint32_t bar, int c0, int c1) {
  asm volatile("cp.async.bulk.tensor.2d.shared::cluster.global.mbarrier::complete_tx::bytes [%0], [%1, {%3, %4}], [%2];" ::"r"(dst), "l"(m), "r"(bar), "r"(c0), "r"(c1) : "memory");
}
__device__ __forceinline__ void tma2_mc(uint32_t dst, const CUtensorMap* m, uint32_t bar, int c0, int c1, uint64_t pol) {
  asm volatile("cp.async.bulk.tensor.2d.shared::cluster.global.mbarrier::complete_tx::bytes.multicast::cluster.L2::cache_hint [%0], [%1, {%3, %4}], [%2], %5, %6;" ::"r"(dst), "l"(m), "r"(bar), "r"(c0), "r"(c1), "h"((uint16_t)3), "l"(pol) : "memory");
}
__device__ __forceinline__ void tma3_mc(uint32_t dst, const CUtensorMap* m, uint32_t bar, int c0, int c1, int c2) {
  asm volatile("cp.async.bulk.tensor.3d.shared::cluster.global.mbarrier::complete_tx::bytes.multicast::cluster [%0], [%1, {%3, %4, %5}], [%2], %6;" ::"r"(dst), "l"(m), "r"(bar), "r"(c0), "r"(c1), "r"(c2), "h"((uint16_t)3) : "memory");
}
__device__ __forceinline__ void tma5_mc(uint32_t dst, const CUtensorMap* m, uint32_t bar, int c0, int c1, int c4, uint64_t pol) {
  asm volatile("cp.async.bulk.tensor.5d.shared::cluster.global.mbarrier::complete_tx::bytes.multicast::cluster.L2::cache_hint [%0], [%1, {%3, %8, %5, %5, %4}], [%2], %6, %7;" ::"r"(dst), "l"(m), "r"(bar), "r"(c0), "r"(c4), "r"(0), "h"((uint16_t)3), "l"(pol), "r"(c1) : "memory");
}
__device__ __forceinline__ void bulk_mc(uint32_t dst, const void* src, uint32_t bytes, uint32_t bar, uint64_t pol) {
  asm volatile("cp.async.bulk.shared::cluster.global.mbarrier::complete_tx::bytes.multicast::cluster.L2::cache_hint [%0], [%1], %2, [%3], %4, %5;" ::"r"(dst), "l"(src), "r"(bytes), "r"(bar), "h"((uint16_t)3), "l"(pol) : "memory");
}
__device__ __forceinline__ void bulk_ld(uint32_t dst, const void* src, uint32_t bytes, uint32_t bar, uint64_t pol) {
  asm volatile("cp.async.bulk.shared::cluster.global.mbarrier::complete_tx::bytes.L2::cache_hint [%0], [%1], %2, [%3], %4;" ::"r"(dst), "l"(src), "r"(bytes), "r"(bar), "l"(pol) : "memory");
}
__device__ __forceinline__ uint32_t ld_acq(const uint32_t* p) { uint32_t v; asm volatile("ld.acquire.gpu.global.u32 %0, [%1];" : "=r"(v) : "l"(p) : "memory"); return v; }
__device__ __forceinline__ void red_rel(uint32_t* p) { asm volatile("red.release.gpu.global.add.u32 [%0], 1;" ::"l"(p) : "memory"); }
__device__ __forceinline__ void wait_cnt(const uint32_t* p, uint32_t target) {
#pragma unroll 1
  while ((int)(ld_acq(p) - target) < 0) {}
}
__device__ __forceinline__ uint4 ldcg4(const void* p) { uint4 v; asm volatile("ld.relaxed.gpu.global.v4.u32 {%0,%1,%2,%3}, [%4];" : "=r"(v.x), "=r"(v.y), "=r"(v.z), "=r"(v.w) : "l"(p) : "memory"); return v; }
__device__ __forceinline__ uint32_t ldcg1(const void* p) { uint32_t v; asm volatile("ld.relaxed.gpu.global.u32 %0, [%1];" : "=r"(v) : "l"(p) : "memory"); return v; }

#define REDE 0
#define PFSTEP 1750u
#define XTN 1152
#define ROTP 1
#define PFN 3
#define WDJIT 1
#define HPF 1
#define ZDELAY 22
#define NGLU 4
#define QPOS 7
#define QN 2
#define KVDELAY 100
#define LS 3
#define KVMC 1
#define XCP 3
#define PFDN 1
#define RDQ "1"
#define ZSLEEP 100
#define RTOP none
#define RPRE red
#define REDOP "red.global.add.v4.f32"
#define ROT (4 * pair)
#define KVPOL poln
#define DBG(v)
#define PFD 24
#define EVICT "evict_first"
#define PWAIT mbar_sleep
__device__ __forceinline__ uint2 ldcg2(const void* p) { uint2 v; asm volatile("ld.relaxed.gpu.global.v2.u32 {%0,%1}, [%2];" : "=r"(v.x), "=r"(v.y) : "l"(p) : "memory"); return v; }

__device__ __forceinline__ void attn_row_exact(Scratch& G, int cta, int m, int j, int w8, int hl, int g, int half, bool late) {
  const int lane = threadIdx.x & 31, head = 4 * j + hl;
  uint32_t q[12];
#pragma unroll
  for (int w = 0; w < 12; w++) {
    const int ln = 4 * g + (w & 3);
    q[w] = ldcg1(G.qb + ((cta * 8 + w8) * 4 + hl) * 192 + (w >> 2) * 64 + ln * 2 + half);
  }
  float mx = -INFINITY, o[19];
#pragma unroll
  for (int d = 0; d < 19; d++) o[d] = 0.f;
#pragma unroll 1
  for (int it = 0; it < 128; it++) {
    if (it == 64) { for (int s = 16; s; s >>= 1) mx = fmaxf(mx, __shfl_xor_sync(~0u, mx, s)); }
    const int key = (it & 63) * 32 + lane;
    const size_t off = (size_t)head * 98304 + (key >> 3) * 384 + (key & 7) * 16;
    float s = 0.f;
#pragma unroll
    for (int c = 0; c < 3; c++) {
      const uint4 a = ldcg4(G.k + off + c * 128);
      s += blo(q[4 * c]) * blo(a.x) + bhi(q[4 * c]) * bhi(a.x) + blo(q[4 * c + 1]) * blo(a.y) + bhi(q[4 * c + 1]) * bhi(a.y) +
           blo(q[4 * c + 2]) * blo(a.z) + bhi(q[4 * c + 2]) * bhi(a.z) + blo(q[4 * c + 3]) * blo(a.w) + bhi(q[4 * c + 3]) * bhi(a.w);
    }
    if (it < 64) mx = fmaxf(mx, s);
    else {
      const float p = bround(ex2(s - mx));
#pragma unroll
      for (int c = 0; c < 2; c++) {
        const uint4 a = ldcg4(G.v + off + c * 128);
        o[8 * c] += p * blo(a.x); o[8 * c + 1] += p * bhi(a.x); o[8 * c + 2] += p * blo(a.y); o[8 * c + 3] += p * bhi(a.y);
        o[8 * c + 4] += p * blo(a.z); o[8 * c + 5] += p * bhi(a.z); o[8 * c + 6] += p * blo(a.w); o[8 * c + 7] += p * bhi(a.w);
      }
      const uint32_t e = ldcg1(G.v + off + 256 + hl * 4);
      o[16] += p * blo(e); o[17] += p * bhi(e); o[18] += p;
    }
  }
#pragma unroll
  for (int d = 0; d < 19; d++)
#pragma unroll 1
    for (int s = 16; s; s >>= 1) o[d] += __shfl_xor_sync(~0u, o[d], s);
  if (lane == 0) {
    const float inv = rcp(o[18]);
#pragma unroll
    for (int t = 0; t < 4; t++) {
      const uint32_t w0 = pack(o[2 * t] * inv, o[2 * t + 1] * inv), w1 = pack(o[8 + 2 * t] * inv, o[9 + 2 * t] * inv);
      if (hl < 3) stg2(G.oe + (m * 6 + hl * 2 + (j >> 2)) * 16384 + (w8 * 16 + g + 8 * half) * 128 + (((2 * (j & 3) + (t >> 1)) ^ g) << 4) + (t & 1) * 8, w0, w1);
      else { uint32_t* ob = G.o + (((m * 8 + w8) * 8 + j) * 32 + g * 4 + t) * 4 + half; ob[0] = w0; ob[2] = w1; }
    }
    if (late) G.ol[(((m * 8 + w8) * 8 + j) * 32 + g * 4 + hl) * 2 + half] = pack(o[16] * inv, o[17] * inv);
  }
}

__device__ __forceinline__ void hmma(float (&c)[4], const uint32_t (&a)[4], uint32_t b0, uint32_t b1) {
  asm("mma.sync.aligned.m16n8k16.row.col.f32.bf16.bf16.f32 {%0,%1,%2,%3}, {%4,%5,%6,%7}, {%8,%9}, {%0,%1,%2,%3};"
      : "+f"(c[0]), "+f"(c[1]), "+f"(c[2]), "+f"(c[3]) : "r"(a[0]), "r"(a[1]), "r"(a[2]), "r"(a[3]), "r"(b0), "r"(b1));
}
template <int N> struct I_ { static constexpr int value = N; };
__device__ __forceinline__ void cpwait(int n) {
  switch (n) {
    case 0: asm volatile("cp.async.wait_group 0;" ::: "memory"); break; case 1: asm volatile("cp.async.wait_group 1;" ::: "memory"); break;
    case 2: asm volatile("cp.async.wait_group 2;" ::: "memory"); break; case 3: asm volatile("cp.async.wait_group 3;" ::: "memory"); break;
    case 4: asm volatile("cp.async.wait_group 4;" ::: "memory"); break; case 5: asm volatile("cp.async.wait_group 5;" ::: "memory"); break;
    case 6: asm volatile("cp.async.wait_group 6;" ::: "memory"); break; case 7: asm volatile("cp.async.wait_group 7;" ::: "memory"); break;
    default: asm volatile("cp.async.wait_group 8;" ::: "memory"); break;
  }
}
struct T_ { static constexpr bool value = true; };
struct F_ { static constexpr bool value = false; };

__global__ void __cluster_dims__(2, 1, 1) __launch_bounds__(384, 1)
fused_kernel(const __grid_constant__ Maps maps, const Ptrs ptrs) {
  extern __shared__ __align__(1024) uint8_t smem[];
  const uint32_t sb = (uint32_t)__cvta_generic_to_shared(smem);
  const uint32_t bars = sb + SM_BAR;
  const int cta = blockIdx.x;
  Scratch& G = *ptrs.s;
  const int rank = cta & 1, j = (cta >> 1) & 7, m = ((cta >> 4) << 1) | rank;
  auto dn_block = [&](int p) { const int q = ROTP * (j < 5 ? j : j - 5), gp = q + p < 5 ? q + p : q + p - 5; return 14 * gp + (gp > q ? 2 : 0); };
  const int wg = __shfl_sync(~0u, threadIdx.x >> 7, 0);

  if (threadIdx.x < 256) {
    const uint32_t r = (threadIdx.x >> 5) * 16 + ((threadIdx.x & 31) >> 3), c = threadIdx.x & 7;
    const uint8_t* src = ptrs.x + (size_t)(m * 128 + r) * (DM * 2) + c * 16;
#pragma unroll
    for (int b = 0; b < XCP; b++) {
#pragma unroll
      for (int q = 0; q < 4; q++)
        asm volatile("cp.async.cg.shared.global [%0], [%1], 16;" ::"r"(sb + SM_XN + b * 16384 + (r + 4 * q) * 128 + ((c ^ ((r + 4 * q) & 7)) << 4)), "l"(src + q * 4 * (DM * 2) + b * 128) : "memory");
      asm volatile("cp.async.commit_group;" ::: "memory");
    }
  } else if (threadIdx.x == 256) {
    for (int b = 0; b < 9; b++) mbar_init(bars + B_X + 8 * b, 1);
    asm volatile("fence.proxy.async.shared::cta;" ::: "memory");
    for (int b = XCP; b < 9; b++) { mbar_expect(bars + B_X + 8 * b, 16384); tma2(sb + SM_XN + b * 16384, &maps.x, bars + B_X + 8 * b, b * 64, m * 128); }
    for (int b = 0; b < XCP; b++) mbar_arrive(bars + B_X + 8 * b);
  } else if (threadIdx.x == 288) {
    l2_prefetch(ptrs.wqkv + cta * 15552, 15552);
    for (int i = 0; i < 4; i++) { mbar_init(bars + B_WFULL + 8 * i, 2); mbar_init(bars + B_HD + 8 * i, 8); mbar_init(bars + B_WEMPTY + 8 * i, 4); mbar_init(bars + B_KEMPTY + 8 * i, 4); }
    mbar_init(bars + B_LEFT, 32); mbar_init(bars + B_KVDONE, 8); mbar_init(bars + B_OEARLY, 8);
    mbar_init(bars + B_FFNDONE, 8); mbar_init(bars + B_LATE, 8); mbar_init(bars + B_FFNOK, 1); mbar_init(bars + B_ZOK, 1); mbar_init(bars + B_XS, 32); mbar_init(bars + B_DONE, 11); mbar_init(bars + B_STG, 2); mbar_init(bars + B_QW, 1); mbar_init(bars + B_EARLYOK, 1); mbar_init(bars + B_XD, 8); mbar_init(bars + B_KV0, 2); mbar_init(bars + B_LEFT2, 32);
    asm volatile("fence.mbarrier_init.release.cluster;" ::: "memory");
  }
  else if (threadIdx.x >= 320 && threadIdx.x < 327) asm volatile("prefetch.tensormap [%0];" ::"l"(&maps.qkv + (threadIdx.x - 320)) : "memory");
  __syncthreads();
  asm volatile("barrier.cluster.arrive.relaxed.aligned;" ::: "memory");

  if (__builtin_expect(wg == 2, 1)) {
    asm volatile("setmaxnreg.dec.sync.aligned.u32 24;");
    const uint32_t epoch = G.epoch[cta] + 1;
    uint64_t pol, poln;
    asm volatile("createpolicy.fractional.L2::evict_normal.b64 %0, 1.0;" : "=l"(poln));
    asm volatile("createpolicy.fractional.L2::" EVICT ".b64 %0, 1.0;" : "=l"(pol));
    auto kv_send = [&](int q0, int q1, uint32_t* cnt) {
#pragma unroll 1
      for (int q = q0; q < q1; q++)
        asm volatile("cp.async.bulk.global.shared::cta.bulk_group [%0], [%1], 6144;" ::"l"((q & 1 ? G.v : G.k) + (size_t)(4 * j + (q >> 1)) * 98304 + m * 6144),
                     "r"(sb + SM_XN + 5 * 16384 + q * 6144) : "memory");
      asm volatile("cp.async.bulk.commit_group;\ncp.async.bulk.wait_group.read 0;" ::: "memory");
      mbar_arrive(bars + B_STG);
      asm volatile("cp.async.bulk.wait_group 0;\nfence.proxy.async.global;" ::: "memory");
      if (q0 == 0) {
        uint32_t peer;
        asm volatile("mapa.shared::cluster.u32 %0, %1, %2;" : "=r"(peer) : "r"(bars + B_KV0), "r"(rank ^ 1));
        mbar_arrive_cl(peer); mbar_arrive(bars + B_KV0);
      }
      red_rel(cnt);
    };
    const CUtensorMap* mgu = rank ? &maps.wu : &maps.wg;
    const int pw = __shfl_sync(~0u, threadIdx.x >> 5, 0);
    asm volatile("barrier.cluster.wait.aligned;" ::: "memory");
    if (pw == 8) {
      uint32_t c = 4;
      auto acquire = [&]() { PWAIT(bars + B_WEMPTY + (c & 3) * 8, (c >> 2) & 1); };
      const uint32_t dst0 = sb + SM_W + rank * 8192;
#pragma unroll 1
      for (int f = 0; f < 10; f++, c++) {
        const uint32_t full = bars + B_WFULL + (c & 3) * 8;
        acquire();
        if (elect()) {
          mbar_expect(full, f < 9 ? 16384 : 8192);
          if (f < 9 || rank == 0) tma2_mc(dst0 + (c & 3) * 16384, &maps.qkv, full, 72 * j + (f < 9 ? (1 + rank) * DM : 0), (f < 9 ? f : 8) * 64, poln);
          mbar_arrive(full);
        }
        if (f >= QPOS && f < QPOS + 4 / QN && elect()) {
          if (f == QPOS) mbar_expect(bars + B_QW, 65536);
#pragma unroll 1
          for (int q = (f - QPOS) * QN; q < (f - QPOS + 1) * QN; q++) tma2_mc(sb + SM_XN + q * 16384 + rank * 8192, &maps.qkv, bars + B_QW, 72 * j, (2 * q + rank) * 64, poln);
        }
      }
#pragma unroll 1
      for (int f = 0, col = DM * j, row = 0; f < 81; f++, c++) {
        const uint32_t full = bars + B_WFULL + (c & 3) * 8;
        acquire();
        if (elect()) {
          mbar_expect(full, 16384); tma2_mc(dst0 + (c & 3) * 16384, mgu, full, col, row, pol);
          if (f < NPRE) mbar_arrive(full);
        }
        row += 64; if (row == DM) { row = 0; col += 64; }
      }
#pragma unroll 1
      for (int f = 0; f < 56; f++, c++) {
        const int p = f / 9, kb = f - 9 * p;
        const uint32_t full = bars + B_WFULL + (c & 3) * 8, dst = dst0 + (c & 3) * 16384;
        if (f < 10 || (f >= 45 && f < 51)) {
          PWAIT(bars + (f == 9 ? B_ZOK : (f == 8 ? B_HD + 24 : B_X + 8 * kb)), f < 8);
          asm volatile("fence.proxy.async.global;" ::: "memory");
        }
        acquire();
        if (elect()) {
          mbar_expect(full, f == 8 ? 32768 : 16384);
          if (f < 53) tma5_mc(dst, f < 45 ? &maps.wd : &maps.woe, full, (f < 45 ? 8 * dn_block(p) : 72 * j) + rank * 64, f < 45 ? 0 : 18 * (kb >> 1),
                              f < 45 ? 18 * j + 2 * kb : (kb < 6 ? 4 * (kb & 1) : 8), pol);
          else tma3_mc(dst, f < 55 ? &maps.woa : &maps.wob, full, 72 * j + 64 * rank, f < 55 ? 54 : 16, f == 54 ? 4 : 0);
          if (f >= 54) mbar_arrive(full);
          if (f == 8) bulk_ld(sb + SM_XN + 8 * 16384, G.h + ((size_t)cta * 9 + 8) * 16384, 16384, full, pol);
        }
      }
      if (elect()) mbar_arrive(bars + B_DONE);
    } else if (pw == 9) {
      const int pair = cta >> 4;
      mbar_wait(bars + B_KV0, 0);
      asm volatile("fence.proxy.async.global;" ::: "memory");
      uint32_t st8 = 0, ph = 0;
      const uint8_t* src = (KVMC && rank ? G.v : G.k) + (size_t)j * 4 * 98304;
      int pos = -1 - (KVMC ? rank : 0);
      uint32_t poff = (size_t)j * 4 * 98304 + 4 * pair * 3072;
#pragma unroll 1
      for (int e = 0; e <= 132; e++) {
        const uint8_t* p = src + ((max(pos, 0) + 4 * pair) & 31) * 3072;
        PWAIT(bars + B_KEMPTY + st8, ph);
        if (elect()) {
          const uint32_t full = bars + B_WFULL + ((e + 10 + NPRE) & 3) * 8;
          mbar_expect(full, 6144);
          if (KVMC) bulk_mc(sb + SM_KV + rank * 3072 + st8 * 768, p, 3072, full, poln);
          else { bulk_ld(sb + SM_KV + st8 * 768, p, 3072, full, poln); bulk_ld(sb + SM_KV + 3072 + st8 * 768, G.v + poff, 3072, full, poln); }
        }
        poff = p - G.k;
        if ((e >= 74 && e < 82) || (e >= 119 && e < 125)) {
          const int bx = e < 82 ? e - 74 : e - 119;
          if (e == 74 || e == 81 || e == 119) {
            PWAIT(bars + (e == 119 ? B_EARLYOK : B_HD + (e == 74 ? 8 : 16)), 0);
            asm volatile("fence.proxy.async.global;" ::: "memory");
          }
          if (elect()) {
            mbar_expect(bars + B_X + 8 * bx, 16384);
            bulk_ld(sb + SM_XN + bx * 16384, e < 82 ? G.h + ((size_t)cta * 9 + bx) * 16384 : G.oe + (m * 6 + bx) * 16384, 16384, bars + B_X + 8 * bx, pol);
          }
        }
        st8 += 8; if (st8 == 24) { st8 = 0; ph ^= 1; }
        if (++pos == 32 && e < 131) { pos = -1; src += 98304; }
        if ((e & 3) == 2 && e < 32) {
          if (e < 28) wait_cnt(&G.cnt_kv0[((((pair + 1 + (e >> 2)) & 7) << 3) | j) * 32], epoch * 2);
          else { wait_cnt(&G.cnt_kv[j * 32], epoch * 16); G.epoch[cta] = epoch; }
          asm volatile("fence.proxy.async.global;" ::: "memory");
        }
      }
#pragma unroll 4
      for (int q = threadIdx.x & 31; q < XTN; q += 32) {
        const int r = q / 9, ch = q - 9 * r;
        asm volatile("cp.async.cg.shared.global [%0], [%1], 16;" ::"r"(sb + SM_XT + q * 16), "l"(ptrs.x + (size_t)(m * 128 + r) * (DM * 2) + j * 144 + ch * 16) : "memory");
      }
      asm volatile("cp.async.wait_all;" ::: "memory");
      mbar_arrive(bars + B_XS);
      if (elect()) mbar_arrive(bars + B_DONE);
    } else if (pw == 10) {
      const int lane = threadIdx.x & 31;
      PWAIT(bars + B_WFULL + 24, 0);
#pragma unroll 1
      for (int w8 = 0; w8 < 8; w8++) {
        stg4(G.o + (((m * 8 + w8) * 8 + j) * 32 + lane) * 4, EMPTY, EMPTY, EMPTY, EMPTY);
        stg2(G.ol + (((m * 8 + w8) * 8 + j) * 32 + lane) * 2, EMPTY, EMPTY);
      }
      __syncwarp();
      mbar_wait(bars + B_KVDONE, 0);
      if (lane == 0) kv_send(0, 2, &G.cnt_kv0[(cta >> 1) * 32]);
      __syncwarp();
#pragma unroll 1
      for (int q = 0; q < ZDELAY; q++) __nanosleep(1000);
#pragma unroll 1
      for (int q = 0; q < 72; q++) {
        __nanosleep(ZSLEEP);
        stg4(reinterpret_cast<float4*>(G.down) + ((size_t)(m * 8 + (q & 7)) * 72 + 9 * j + (q >> 3)) * 32 + lane, 0, 0, 0, 0);
      }
      __syncwarp();
      if (lane == 0) {
        red_rel(&G.cnt_zero[m * 32]);
        PWAIT(bars + B_HD + 16, 0);
        wait_cnt(&G.cnt_zero[m * 32], epoch * 8); mbar_arrive(bars + B_ZOK);
      }
      __syncwarp();
      const volatile uint32_t* badv = reinterpret_cast<const volatile uint32_t*>(smem + SM_BAR + B_BAD);
#pragma unroll 1
      for (int ph = 0; ph < 2; ph++) {
        mbar_sleep(bars + (ph ? B_LATE : B_OEARLY), 0);
        const uint32_t mine = (ph == 0 && (lane & 3) == 3) ? 0u : badv[lane];
        uint32_t todo = __ballot_sync(~0u, mine != 0);
        while (todo) {
          const int e = __ffs(todo) - 1; todo &= todo - 1;
          uint32_t rows = __shfl_sync(~0u, mine, e);
          while (rows) { const int r = __ffs(rows) - 1; rows &= rows - 1; attn_row_exact(G, cta, m, j, e >> 2, e & 3, r & 7, r >> 3, ph != 0); }
        }
        __syncwarp();
        if (ph == 0) {
          if (lane == 0) {
            red_rel(&G.cnt_early[m * 32]);
            wait_cnt(&G.cnt_early[m * 32], epoch * 8);
            mbar_arrive(bars + B_EARLYOK);
            mbar_sleep(bars + B_FFNDONE, 0);
            TH(0);
            TH(2);
            red_rel(&G.cnt_ffn[m * 32]);
            TH(3);
            wait_cnt(&G.cnt_ffn[m * 32], epoch * 8);
            mbar_arrive(bars + B_FFNOK);
            TH(4);
          }
          __syncwarp();
        }
      }
      if (lane == 0) mbar_arrive(bars + B_DONE);
    } else {
      const uint8_t* src = ptrs.wqkv + (size_t)(threadIdx.x & 31) * (3 * DM * 2) + (72 * j + 64) * 2;
#pragma unroll 2
      for (int q = 0; q < 18; q++) {
        const uint32_t dst = (q < 12 ? sb + SM_KV + q * 512 : sb + SM_XN + 4 * 16384 + (q - 12) * 512) + (threadIdx.x & 31) * 16, gs = q < 12 ? 6144 : 3072;
        asm volatile("cp.async.cg.shared.global [%0], [%3], 16;\ncp.async.cg.shared.global [%1], [%3+1152], 16;\ncp.async.cg.shared.global [%2], [%3+2304], 16;"
                     ::"r"(dst), "r"(dst + gs), "r"(dst + 2 * gs), "l"(src + (size_t)q * 32 * (3 * DM * 2)) : "memory");
        if (q == 11) {
          asm volatile("cp.async.wait_all;\nfence.proxy.async.shared::cta;" ::: "memory");
          mbar_arrive(bars + B_LEFT);
          mbar_guard(bars + B_XD);
        }
      }
      asm volatile("cp.async.wait_all;\nfence.proxy.async.shared::cta;" ::: "memory");
      mbar_arrive(bars + B_LEFT2);
      const int pair = cta >> 4, lane = threadIdx.x & 31;
      int pp = 0, pk = pair;
      auto prefetch = [&]() {
        if (pp < 9) { const uint8_t* p = (rank ? ptrs.wu : ptrs.wg) + (size_t)(pk * 64 + lane) * (FF * 2) + j * (DM * 2) + pp * 128; pf_line(p); pf_line(p + 32 * FF * 2); }
        else if (pp < 14) {
          const uint8_t* p = ptrs.wd + (size_t)(j * DM + pk * 64 + lane) * (DM * 2) + 16 * dn_block(pp - 9) + rank * 128;
          pf_line(p); pf_line(p + 32 * DM * 2);
          if (rank) { const int o = pp == 9 ? 112 : 80; pf_line(p + o); pf_line(p + 32 * DM * 2 + o); }
        }
        if (pk == 0) pk = 8; else { pk--; pp++; }
      };
      prefetch(); prefetch(); prefetch();
      if (lane == 0) {
        mbar_guard(bars + B_KVDONE);
        __nanosleep(KVDELAY);
        kv_send(2, 8, &G.cnt_kv[j * 32]);
      }
      __syncwarp();
      uint32_t t0;
      asm volatile("mov.u32 %0, %%globaltimer_lo;" : "=r"(t0));
#pragma unroll 1
      for (int q = 1; q < 28; q++) {
        uint32_t t1;
        do { __nanosleep(200); asm volatile("mov.u32 %0, %%globaltimer_lo;" : "=r"(t1)); } while (t1 - t0 < q * PFSTEP && t1 - t0 < 1000000u);
        if (q & 1) prefetch();
        if (q == 22 || q == 24) pf_line(ptrs.wo + min(cta * 5184 + (q - 22) * 2048 + lane * 128, DM * DM * 2 - 128));
      }
      if (lane == 0) mbar_guard(bars + B_DONE);
    }
  } else {
    TS(0);
    asm volatile("setmaxnreg.inc.sync.aligned.u32 240;");
    TQ(60);
    uint32_t A[36][4];
    const uint32_t lm_base = sb + SM_XN + ((threadIdx.x >> 5) * 16 + (threadIdx.x & 15)) * 128;
    const uint32_t lm_x = ((threadIdx.x >> 4) & 1) ^ (threadIdx.x & 7);
    uint32_t mm[2], rh[2], rl[2];
    auto x_load = [&](int b) {
#pragma unroll
      for (int kk = 0; kk < 4; kk++) {
        uint32_t(&a)[4] = A[4 * b + kk];
        asm volatile("ldmatrix.sync.aligned.m8n8.x4.shared.b16 {%0,%1,%2,%3}, [%4];" : "=r"(a[0]), "=r"(a[1]), "=r"(a[2]), "=r"(a[3]) : "r"(lm_base + b * 16384 + ((lm_x ^ (2 * kk)) << 4)) : "memory");
      }
    };
    {
      float c[6][4];
#pragma unroll
      for (int i = 0; i < 24; i++) c[i >> 2][i & 3] = 0.f;
#pragma unroll
      for (int b = 0; b < 9; b++) {
        if (b < XCP) { cpwait(XCP - 1 - b); __syncwarp(); } else mbar_wait(bars + B_X + 8 * b, 0);
        TQ(61 + b);
        x_load(b);
#pragma unroll
        for (int kk = 0; kk < 4; kk++) {
          const uint32_t(&a)[4] = A[4 * b + kk];
          hmma(c[kk & 1], a, 0x3F803F80u, 0x3F803F80u); hmma(c[2 + (kk & 1)], a, a[0], a[2]); hmma(c[4 + (kk & 1)], a, a[1], a[3]);
        }
      }
      const float s0 = c[0][0] + c[1][0], s1 = c[0][2] + c[1][2];
      const bool odd = (threadIdx.x >> 2) & 1;
      const int dsrc = (threadIdx.x & 28) | ((threadIdx.x >> 3) & 3);
      float q0 = __shfl_sync(~0u, odd ? c[2][1] + c[3][1] : c[2][0] + c[3][0], dsrc), q1 = __shfl_sync(~0u, odd ? c[4][3] + c[5][3] : c[4][2] + c[5][2], dsrc);
      TS(1);
      const float mu0 = s0 * (1.0f / DM), mu1 = s1 * (1.0f / DM);
      float var0 = fmaf(-mu0, mu0, q0 * (1.0f / DM)), var1 = fmaf(-mu1, mu1, q1 * (1.0f / DM));
      if (__any_sync(~0u, var0 < 0.01f * mu0 * mu0 || var1 < 0.01f * mu1 * mu1)) {
        q0 = 0.f; q1 = 0.f;
#pragma unroll 1
        for (int k = 0; k < 36; k++) {
          uint32_t u[4];
          asm volatile("ldmatrix.sync.aligned.m8n8.x4.shared.b16 {%0,%1,%2,%3}, [%4];" : "=r"(u[0]), "=r"(u[1]), "=r"(u[2]), "=r"(u[3]) : "r"(lm_base + (k >> 2) * 16384 + ((lm_x ^ (2 * (k & 3))) << 4)) : "memory");
#pragma unroll
          for (int i = 0; i < 4; i++) {
            const float mu = (i & 1) ? mu1 : mu0, lo = blo(u[i]) - mu, hi = bhi(u[i]) - mu;
            if (i & 1) q1 += lo * lo + hi * hi; else q0 += lo * lo + hi * hi;
          }
        }
#pragma unroll
        for (int s = 1; s < 4; s <<= 1) { q0 += __shfl_xor_sync(~0u, q0, s); q1 += __shfl_xor_sync(~0u, q1, s); }
        var0 = q0 * (1.0f / DM); var1 = q1 * (1.0f / DM);
      }
      if ((threadIdx.x & 31) == 0) mbar_arrive(bars + B_XD);
      const float r0 = rcp(bround(fsqrt(bround(bround(var0) + 1e-5f)))), r1 = rcp(bround(fsqrt(bround(bround(var1) + 1e-5f))));
      const float h0 = bround(r0), h1 = bround(r1);
      mm[0] = pack(mu0, mu0); mm[1] = pack(mu1, mu1); rh[0] = pack(h0, h0); rh[1] = pack(h1, h1); rl[0] = pack(r0 - h0, r0 - h0); rl[1] = pack(r1 - h1, r1 - h1);
    }
    auto normalize = [&](int b) {
#pragma unroll
      for (int kk = 0; kk < 4; kk++)
#pragma unroll
        for (int i = 0; i < 4; i++) { const uint32_t d = hsub2(A[4 * b + kk][i], mm[i & 1]); A[4 * b + kk][i] = hfma2(d, rh[i & 1], hmul2(d, rl[i & 1])); }
    };
    auto xn_store = [&](int b) {
#pragma unroll
      for (int kk = 0; kk < 4; kk++)
        asm volatile("stmatrix.sync.aligned.m8n8.x4.shared.b16 [%0], {%1,%2,%3,%4};" ::"r"(lm_base + b * 16384 + ((lm_x ^ (2 * kk)) << 4)), "r"(A[4 * b + kk][0]), "r"(A[4 * b + kk][1]), "r"(A[4 * b + kk][2]), "r"(A[4 * b + kk][3]) : "memory");
    };
    asm volatile("barrier.cluster.wait.aligned;" ::: "memory");
    uint32_t tid;
    asm volatile("mov.u32 %0, %%tid.x;" : "=r"(tid));
    const int warp = (tid >> 5) & 3, lane = tid & 31, g = lane >> 2, t = lane & 3;
    const int w8 = tid >> 5;
    uint32_t rel;
    asm volatile("mapa.shared::cluster.u32 %0, %1, %2;" : "=r"(rel) : "r"(bars), "r"(warp & 1));
    uint32_t krel = rel;
    if (!KVMC) asm volatile("mapa.shared::cluster.u32 %0, %1, %2;" : "=r"(krel) : "r"(bars), "r"(rank));
    const bool sig = (tid & 95) == 64;
    const uint32_t w0 = (((sb + SM_W) & 0x3FFFF) >> 4) | (512u << 16), k0 = ((sb + SM_KV) & 0x3FFFF) >> 4;
    const uint32_t a0 = (((sb + SM_XN + wg * 8192) & 0x3FFFF) >> 4) | (1u << 16);
    const uint32_t x0 = (((sb + SM_XN) & 0x3FFFF) >> 4) | (512u << 16);
    uint32_t wc = 0;
    uint32_t ks8 = 0;
    auto w_wait = [&]() { mbar_wait(bars + B_WFULL + (wc & 3) * 8, (wc >> 2) & 1); };
    auto w_desc = [&]() { return mkd(w0 + (wc & 3) * 1024, HI_SW128); };
    auto w_release_prev = [&]() { if (sig) mbar_arrive_cl(rel + B_WEMPTY + ((wc - 1) & 3) * 8); };
    TS(2);
    float acc[64];
    uint32_t Qx[6];
    uint32_t* const qb = G.qb + (size_t)(cta * 8 + w8) * 4 * 192 + lane * 2;
    {
      float lf[12];
      const int rtz = ptrs.one - 1;
      const uint64_t da8 = mkd(a0 + 8 * 1024, HI_SW128);
      normalize(8); xn_store(8);
#pragma unroll
      for (int i = 0; i < 64; i++) acc[i] = 0.f;
#pragma unroll
      for (int i = 0; i < 12; i++) lf[i] = 0.f;
      keep(acc); keep(lf);
      normalize(0);
#pragma unroll
      for (int s = 0; s < 9; s++) {
        TQ(2 * s);
        if (s == LS) mbar_wait(bars + B_LEFT, 0);
        if (s == 7) mbar_wait(bars + B_LEFT2, 0);
        w_wait();
        TQ(2 * s + 1);
        WG_FENCE();
        const uint64_t db = w_desc();
#pragma unroll
        for (int kk = 0; kk < 4; kk++) {
          const int k = 4 * s + kk;
          if (s < 8) mma_rs128_t(acc, A[k][0], A[k][1], A[k][2], A[k][3], db + kk * 128, k != 0);
          else mma_ss128_t(acc, da8 + kk * 2, db + kk * 128, 1);
          if (s >= LS) {
#pragma unroll
            for (int q = (k - 4 * LS) * 9 / (9 - LS); q < (k - 4 * LS + 1) * 9 / (9 - LS); q++) {
              const uint64_t dl = q < 24 ? mkd(k0 | (8u << 16), 384u) + q * 16 : mkd(((x0 & 0x3FFF) + 4096) | (8u << 16), 192u) + (q - 24) * 16;
              if (q < 32) mma_rs24_t(lf, A[q][0], A[q][1], A[q][2], A[q][3], dl, q != 0);
              else mma_ss24_t(lf, da8 + (q - 32) * 2, dl, 1);
            }
          }
        }
        WG_COMMIT();
        if (s < 7) normalize(s + 1);
        if (s == 7) { asm volatile("fence.proxy.async.shared::cta;" ::: "memory"); asm volatile("bar.sync %0, 128;" ::"r"(1 + wg) : "memory"); }
        if (s > 0) { WG_WAIT(1); w_release_prev(); }
        wc++;
      }
      WG_WAIT(0); keep(acc); keep(lf);
      w_release_prev();
      TS(3); TQ(18);
      uint8_t* const stg = smem + SM_XN + 5 * 16384 + w8 * 768 + g * 16;
      auto kv_stage = [&](int e) {
        uint32_t u[9];
#pragma unroll
        for (int b = 0; b < 8; b++) u[b] = pack(acc[32 * (e >> 1) + 4 * b + 2 * (e & 1)], acc[32 * (e >> 1) + 4 * b + 2 * (e & 1) + 1]);
        u[8] = pack(lf[4 + 2 * e], lf[5 + 2 * e]);
        const uint32_t one = e >> 1 ? 0x00003F80u : 0x3F803F80u;
#pragma unroll
        for (int hl = 0; hl < 4; hl++) {
          uint8_t* const q = stg + hl * 12288 + (e >> 1) * 6144 + (e & 1) * 384;
          uint32_t* p = reinterpret_cast<uint32_t*>(q) + (e >> 1 ? ((t - hl) & 3) : t);
          p[0] = t < hl ? u[2 * hl + 1] : u[2 * hl];
          p[32] = t < hl ? u[2 * hl + 2] : u[2 * hl + 1];
          reinterpret_cast<uint32_t*>(q + 256)[t] = t == hl ? u[2 * hl + 2] : (t == ((hl + 1) & 3) ? one : 0u);
        }
      };
      kv_stage(0); kv_stage(1);
      TQ(20);
      w_wait();
      mbar_wait(bars + B_QW, 0);
      TQ(21);
      WG_FENCE();
      uint64_t dq = mkd(x0, HI_SW128);
      asm volatile("" : "+l"(dq));
      {
        const uint64_t db = w_desc();
#pragma unroll
        for (int kk = 0; kk < 4; kk++) mma_ss64_t(acc, da8 + kk * 2, db + kk * 128, kk ? 1 : rtz);
        WG_COMMIT();
      }
      wc++;
#pragma unroll
      for (int k = 0; k < 32; k++) {
        mma_rs64_t(acc, A[k][0], A[k][1], A[k][2], A[k][3], dq + k * 128, 1);
        if (k == 3) {
          WG_COMMIT();
          kv_stage(2); kv_stage(3);
          asm volatile("fence.proxy.async.shared::cta;" ::: "memory");
          __syncwarp();
          if (lane == 0) mbar_arrive(bars + B_KVDONE);
          if (sig) { mbar_arrive_cl(krel + B_KEMPTY); mbar_arrive_cl(krel + B_KEMPTY + 8); }
          WG_WAIT(1); w_release_prev();
        }
      }
      WG_COMMIT();
      TQ(22);
      WG_WAIT(0); keep(acc);
      TS(4);
      uint32_t u[2][9];
#pragma unroll
      for (int r = 0; r < 2; r++) {
#pragma unroll
        for (int b = 0; b < 8; b++) u[r][b] = pack(acc[4 * b + 2 * r] * QSCALE, acc[4 * b + 2 * r + 1] * QSCALE);
        u[r][8] = pack(lf[2 * r] * QSCALE, lf[2 * r + 1] * QSCALE);
      }
      asm volatile("bar.sync 3, 256;" ::: "memory");
      xn_store(2); xn_store(3);
      TQ(23);
#pragma unroll
      for (int s = 0; s < NPRE; s++) {
        w_wait();
        if (s == 0 && sig) mbar_arrive_cl(krel + B_KEMPTY + 16);
        WG_FENCE();
        const uint64_t db = w_desc();
#pragma unroll
        for (int kk = 0; kk < 4; kk++) mma_rs128_t(acc, A[4 * s + kk][0], A[4 * s + kk][1], A[4 * s + kk][2], A[4 * s + kk][3], db + kk * 128, (s | kk) ? 1 : rtz);
        WG_COMMIT();
        wc++;
      }
      TQ(24);
      xn_store(4); xn_store(0);
      TQ(25);
      asm volatile("fence.proxy.async.shared::cta;" ::: "memory");
      asm volatile("bar.sync %0, 128;" ::"r"(1 + wg) : "memory");
#pragma unroll
      for (int hl = 0; hl < 4; hl++) {
        uint32_t q6[6];
#pragma unroll
        for (int r = 0; r < 2; r++) {
          q6[r] = t < hl ? u[r][2 * hl + 1] : u[r][2 * hl];
          q6[2 + r] = t < hl ? u[r][2 * hl + 2] : u[r][2 * hl + 1];
          q6[4 + r] = t == hl ? u[r][2 * hl + 2] : 0u;
        }
#pragma unroll
        for (int e = 0; e < 3; e++) stg2(qb + (hl * 3 + e) * 64, q6[2 * e], q6[2 * e + 1]);
        if (hl == 0) {
#pragma unroll
          for (int e = 0; e < 6; e++) Qx[e] = q6[e];
        }
      }
      TQ(26);
      WG_WAIT(0); keep(acc);
      wc--; w_release_prev(); wc++;
    }
    TS(5);
    w_wait();
    TS(6);
    float S[32], O[12], acc2[64];
    uint32_t P[16], Q[6] = {0, 0, 0, 0, 0, 0}, OL[2] = {0, 0};
    uint32_t zero0 = ptrs.one - 1, zero1 = ptrs.one >> 1;
    asm volatile("" : "+r"(zero0), "+r"(zero1));
#pragma unroll
    for (int i = 0; i < 32; i++) S[i] = 0.f;
#pragma unroll
    for (int i = 0; i < 12; i++) O[i] = 0.f;
#pragma unroll
    for (int i = 0; i < 16; i++) P[i] = 0;
    keep(S); keep(O); keep(acc);
    uint32_t c8 = (10 + NPRE) * 8, s8 = ((10 + NPRE) * 8) & 24, p8 = ((9 + NPRE) * 8) & 24, alo = a0 + NPRE * 1024;
    asm volatile("" : "+r"(c8), "+r"(s8), "+r"(p8), "+r"(alo));
    const uint32_t K0 = k0 | (8u << 16), V0 = (k0 + 192) | (24u << 16);
    auto f_wait = [&]() { mbar_wait(bars + B_WFULL + s8, c8 >> 5); };
    float* const dn_base = G.down + (size_t)(m * 8 + w8) * 72 * 128 + lane * 4;

    auto ffn_issue = [&](auto n112, float (&ac)[64], int sd) {
      const uint64_t da = mkd(alo, HI_SW128), db = mkd(w0 + s8 * 128, HI_SW128);
#pragma unroll
      for (int kk = 0; kk < 4; kk++) {
        if constexpr (decltype(n112)::value) mma_ss112_t(ac, da + kk * 2, db + kk * 128, kk ? 1 : sd);
        else mma_ss128_t(ac, da + kk * 2, db + kk * 128, kk ? 1 : sd);
      }
      WG_COMMIT();
    };
    auto att_issue = [&]() {
      const uint64_t dk = mkd(K0 + ks8 * 48, 24u), dv = mkd(V0 + ks8 * 48, 8u);
#pragma unroll
      for (int kk = 0; kk < 4; kk++) mma_rs24_t(O, P[4 * kk], P[4 * kk + 1], P[4 * kk + 2], P[4 * kk + 3], dv + kk * 48, 1);
      mma_rs64_n(S, Q[0], Q[1], Q[2], Q[3], dk, 0);
      mma_rs64_n(S, Q[4], Q[5], zero0, zero1, dk + 16, 1);
      WG_COMMIT();
    };
    auto o_finalize = [&](int hl, auto last) {
      const int src = (lane & 28) | ((hl + 1) & 3);
      float l0, l1;
      asm volatile("shfl.sync.idx.b32 %0, %1, %2, 31, -1;" : "=f"(l0) : "f"(O[8]), "r"(src));
      asm volatile("shfl.sync.idx.b32 %0, %1, %2, 31, -1;" : "=f"(l1) : "f"(O[10]), "r"(src));
      const float b0 = fabsf(O[0]) + fabsf(O[1]) + fabsf(O[4]) + fabsf(O[5]), c0 = b0 + fabsf(O[8]) + fabsf(O[9]);
      const float b1 = fabsf(O[2]) + fabsf(O[3]) + fabsf(O[6]) + fabsf(O[7]), c1 = b1 + fabsf(O[10]) + fabsf(O[11]);
      const float i0 = rcp(l0), i1 = rcp(l1);
      const uint32_t mine = (!(c0 < INFINITY && b0 > 3e-33f && l0 > 1e-30f && l0 < 1e36f) ? 1u << g : 0u) | (!(c1 < INFINITY && b1 > 3e-33f && l1 > 1e-30f && l1 < 1e36f) ? 256u << g : 0u);
      const uint32_t rows = __reduce_or_sync(~0u, mine);
      const uint32_t e0 = (rows >> g) & 1 ? EMPTY : 0u, e1 = (rows >> g) & 256 ? EMPTY : 0u;
      if constexpr (decltype(last)::value)
        stg4(G.o + (((m * 8 + w8) * 8 + j) * 32 + lane) * 4, pack(O[0] * i0, O[1] * i0) | e0, pack(O[2] * i1, O[3] * i1) | e1, pack(O[4] * i0, O[5] * i0) | e0, pack(O[6] * i1, O[7] * i1) | e1);
      else {
        uint8_t* p = G.oe + (m * 6 + hl * 2 + (j >> 2)) * 16384 + (w8 * 16 + g) * 128 + (((2 * (j & 3) + (t >> 1)) ^ g) << 4) + (t & 1) * 8;
        stg2(p, pack(O[0] * i0, O[1] * i0), pack(O[4] * i0, O[5] * i0));
        stg2(p + 1024, pack(O[2] * i1, O[3] * i1), pack(O[6] * i1, O[7] * i1));
      }
      if (t == hl) { OL[0] = pack(O[8] * i0, O[9] * i0) | e0; OL[1] = pack(O[10] * i1, O[11] * i1) | e1; }
      if (lane == 0) *reinterpret_cast<volatile uint32_t*>(smem + SM_BAR + B_BAD + (w8 * 4 + hl) * 4) = rows;
    };
    auto plain_math = [&]() {
#pragma unroll
      for (int b = 0; b < 16; b++) P[b] = pack(ex2(S[2 * b]), ex2(S[2 * b + 1]));
    };
    auto post = [&]() {
      TI();
      if (sig) mbar_arrive_cl(krel + B_KEMPTY + ks8);
      ks8 = ks8 == 16 ? 0 : ks8 + 8;
    };

    auto head_start = [&](int hl) {
      if (hl > 0) o_finalize(hl - 1, F_{});
      __syncwarp();
      if (hl == 3 && lane == 0) mbar_arrive(bars + B_OEARLY);
      float m0 = S[0], m1 = S[2];
#pragma unroll
      for (int b = 0; b < 8; b++) { m0 = fmaxf(m0, fmaxf(S[4 * b], S[4 * b + 1])); m1 = fmaxf(m1, fmaxf(S[4 * b + 2], S[4 * b + 3])); }
#pragma unroll
      for (int s = 1; s < 4; s <<= 1) { m0 = fmaxf(m0, __shfl_xor_sync(~0u, m0, s)); m1 = fmaxf(m1, __shfl_xor_sync(~0u, m1, s)); }
      m0 = -(m0 + MOFF); m1 = -(m1 + MOFF);
      const float h0 = bround(m0), h1 = bround(m1);
      if (t == ((hl + 1) & 3)) { Q[4] = pack(h0, m0 - h0); Q[5] = pack(h1, m1 - h1); }
#pragma unroll
      for (int e = 0; e < 12; e++) O[e] = 0.f;
#pragma unroll
      for (int e = 0; e < 16; e++) P[e] = 0;
      keep(O);
    };
    auto red4 = [&](float* dst, const float* v) {
      asm volatile("red.global.add.v4.f32 [%0], {%1,%2,%3,%4};" ::"l"(dst), "f"(v[0]), "f"(v[1]), "f"(v[2]), "f"(v[3]) : "memory");
    };
    bool ok = true;
    auto probe = [&]() { ok = mbar_test(bars + B_WFULL + s8, c8 >> 5); };
    auto issue = [&](auto fm, float (&cur)[64], int sd, auto top, auto pre) {
      constexpr int FM = decltype(fm)::value;
      if constexpr (FM != 0) WG_WAIT(0);
      WG_FENCE();
      att_issue();
      top();
      if constexpr (FM == 1) ffn_issue(F_{}, cur, sd);
      if constexpr (FM == 2) ffn_issue(T_{}, cur, sd);
      if constexpr (FM != 0) { if (sig) mbar_arrive_cl(rel + B_WEMPTY + p8); }
      p8 = s8; c8 += 8; s8 = c8 & 24; alo += 1024;
      pre();
      if constexpr (FM != 0) { WG_WAIT(1); } else { WG_WAIT(0); }
      keep(S); keep(O);
      post();
    };
    auto once = [&](auto fm, float (&cur)[64], int sd, auto top, auto pre, auto mid) {
      int n = ptrs.one;
      if (!ok) f_wait();
#pragma unroll 1
      do { issue(fm, cur, sd, top, pre); plain_math(); mid(); probe(); } while (--n > 0);
    };
    auto iters = [&](auto fm, float (&cur)[64], int n) {
      bool more;
#pragma unroll 1
      do {
        if (!ok) f_wait();
#pragma unroll 1
        do { issue(fm, cur, 1, [] {}, [] {}); plain_math(); probe(); more = --n != 0; } while (ok && more);
      } while (more);
    };
    auto none = [] {};
    auto hs_iter = [&](auto fm, float (&cur)[64], int hl, auto pre) {
#pragma unroll
      for (int e = 0; e < 6; e++) Q[e] = Qx[e];
      if (!ok) f_wait();
      issue(fm, cur, 1, none, pre);
      probe();
      head_start(hl);
    };
    uint8_t* hp = G.h + (size_t)cta * 9 * 16384 + w8 * 2048 + g * 128 + ((t ^ g) << 4);
    auto glu_iters = [&](float (&cur)[64], float (&prev)[64], int p, auto ldq) {
#pragma unroll
      for (int r = 0; r < NGLU; r++)
        once(I_<1>{}, cur, r ? 1 : (decltype(ldq)::value ? 0 : p == 0), none, [&] {
          if (decltype(ldq)::value && r == 0) {
#pragma unroll
            for (int e = 0; e < 3; e++) { const uint2 v = ldcg2(qb + ((p >> 2) + 1) * 192 + e * 64); Qx[2 * e] = v.x; Qx[2 * e + 1] = v.y; }
          }
        }, [&] {
#pragma unroll
          for (int i = r * 4 / NGLU; i < (r + 1) * 4 / NGLU; i++) {
            uint32_t h[4];
#pragma unroll
            for (int q = 0; q < 4; q++) { const int e = 16 * (i & 1) + 4 * q + 2 * (i >> 1); h[q] = hmul2(pack_relu(prev[e], prev[e + 1]), pack(prev[32 + e], prev[33 + e])); }
            stg4(reinterpret_cast<void*>(reinterpret_cast<uint64_t>(hp + (i >> 1) * 1024) ^ ((i & 1) * 64)), h[0], h[1], h[2], h[3]);
          }
          if (r == NGLU - 1) {
            __syncwarp();
            if (lane == 0) mbar_arrive(bars + B_HD + max(p - 6, 0) * 8);
            hp += p ? 16384 : 0;
          }
        });
    };

    static_assert(NPRE == 1 || NPRE == 2, "heads must start in the plain part of a pass");
    hs_iter(I_<1>{}, acc, 0, [&] {
      xn_store(1);
      mbar_wait(bars + B_STG, 0);
      xn_store(5); xn_store(6); xn_store(7);
    });
    asm volatile("fence.proxy.async.shared::cta;" ::: "memory");
    asm volatile("bar.sync %0, 128;" ::"r"(1 + wg) : "memory");
    WG_WAIT(0); keep(acc);
    if (!ok) f_wait();
    ok = true;
#pragma unroll
    for (int i = 0; i < 64; i++) acc2[i] = 0.f;
    keep(acc2);
#pragma unroll 1
    for (int p = 0; p < 10; p += 2) {
      static_assert(NPRE == 2 && NGLU <= 4, "");
      glu_iters(acc, acc2, p, F_{});
      iters(I_<1>{}, acc, p ? 9 - NGLU : 6 - NGLU);
      alo = a0;
      TP(p);
      glu_iters(acc2, acc, p + 1, T_{});
      iters(I_<1>{}, acc2, p == 2 ? 8 - NGLU : (p == 6 ? 5 - NGLU : 9 - NGLU));
      if (__builtin_expect((p & 3) == 2, 0)) {
        int hl = p;
        asm volatile("shr.u32 %0, %0, 2;" : "+r"(hl));
        hs_iter(I_<1>{}, acc2, hl + 1, none);
        if (p == 6) iters(I_<1>{}, acc2, 3);
      }
      alo = a0;
      TP(p + 1);
    }
    float* dpn = dn_base + dn_block(0) * 128;
#pragma unroll 1
    for (int p = 0; p < 5; p++) {
      float* const dp = dpn;
      float cpy[64];
      once(I_<2>{}, acc2, 0, [&] {
        keep(acc2);
#pragma unroll
        for (int q = 0; q < 64; q++) cpy[q] = acc2[q];
        keep(cpy);
        WG_FENCE();
      }, [&] { if (REDE) { red4(dp, &cpy[0]); red4(dp + 128, &cpy[4]); } }, [&] { dpn = dn_base + dn_block(p + 1) * 128; asm volatile("" : "+l"(dpn)); });
#pragma unroll
      for (int e = REDE; e < 8 + REDE; e++) {
        auto red = [&] { if (e < 7 || (e == 7 && p == 0)) { red4(dp + e * 256, &cpy[8 * e]); red4(dp + e * 256 + 128, &cpy[8 * e + 4]); }
          if (e == 6) { __syncwarp(); if (lane == 0 && p == 4) mbar_arrive(bars + B_FFNDONE); } };
        if (e == 7 + REDE && p == 4) break;
        if (e == NPRE - 1 + REDE && p == 1) hs_iter(I_<2>{}, acc2, 3, red);
        else once(I_<2>{}, acc2, 1, none, red, none);
      }
      alo = a0;
      if (p < 4) TP(10 + p);
    }
    TS(8);
    {
      static_assert(NPRE == 2, "");
      if (!ok) f_wait();
      WG_WAIT(0); keep(acc2);
      const uint32_t wl = c8 >> 3;
      issue(I_<0>{}, acc2, 1, none, none);
      o_finalize(3, T_{});
      stg2(G.ol + (((size_t)(m * 8 + w8) * 8 + j) * 32 + lane) * 2, OL[0], OL[1]);
      __syncwarp();
      if (lane == 0) mbar_arrive(bars + B_LATE);
      TS(9); TQ(54);
      f_wait(); c8 += 8; s8 = c8 & 24; f_wait();
      const uint32_t* obp = G.o + ((size_t)(m * 8 + w8) * 8 * 32 + lane) * 4;
      asm volatile("" : "+l"(obp));
      uint4 B[8]; uint2 L[8];
      const uint32_t* olp = G.ol + ((size_t)(m * 8 + w8) * 8 * 32 + lane) * 2;
      asm volatile("" : "+l"(olp));
#pragma unroll 1
      for (;;) {
#pragma unroll
        for (int k = 0; k < 8; k++) { B[k] = ldcg4(obp + k * 128); L[k] = ldcg2(olp + k * 64); }
        uint32_t mx = 0;
#pragma unroll
        for (int k = 0; k < 8; k++) mx = max(max(max(mx, B[k].x), max(B[k].y, B[k].z)), max(max(B[k].w, L[k].x), L[k].y));
        if (!__any_sync(~0u, mx == EMPTY)) break;
      }
      TS(10); TQ(56);
      WG_FENCE();
#pragma unroll
      for (int k = 0; k < 8; k++) mma_rs72w_t(acc2, B[k].x, B[k].y, B[k].z, B[k].w, mkd(w0 + ((wl + (k >> 2)) & 3) * 1024, HI_SW128) + (k & 3) * 128, 1);
#pragma unroll
      for (int k = 0; k < 4; k++) mma_rs72w_t(acc2, L[2 * k].x, L[2 * k].y, L[2 * k + 1].x, L[2 * k + 1].y, mkd(w0 + ((wl + 2) & 3) * 1024, HI_SW128) + k * 128, 1);
      WG_COMMIT();
      mbar_wait(bars + B_FFNOK, 0);
      TQ(55);
      uint4 d[9];
      const float* dnj = dn_base + 9 * j * 128;
      asm volatile("" : "+l"(dnj));
#pragma unroll
      for (int b = 0; b < 9; b++) d[b] = ldcg4(dnj + b * 128);
      mbar_wait(bars + B_XS, 0);
      if (lane == 0) mbar_arrive(bars + B_DONE);
      uint32_t* xt = reinterpret_cast<uint32_t*>(smem + SM_XT + (w8 * 16 + g) * 144) + t;
      uint32_t xr[9][2], gt[9][2];
#pragma unroll
      for (int b = 0; b < 9; b++) { xr[b][0] = xt[4 * b]; xr[b][1] = xt[4 * b + 288]; }
#pragma unroll
      for (int b = 0; b < 9; b++) {
        float v[4] = {bround(__uint_as_float(d[b].x)), bround(__uint_as_float(d[b].y)), bround(__uint_as_float(d[b].z)), bround(__uint_as_float(d[b].w))};
#pragma unroll
        for (int q = 0; q < 4; q++) v[q] = v[q] * rcp(1.0f + ex2(-1.4426950408889634f * v[q]));
        gt[b][0] = pack(v[0], v[1]); gt[b][1] = pack(v[2], v[3]);
      }
      WG_WAIT(0); keep(acc2);
      TQ(57);
#pragma unroll
      for (int b = 0; b < 9; b++) {
        xt[4 * b] = hadd2(xr[b][0], hmul2(pack(acc2[4 * b], acc2[4 * b + 1]), gt[b][0]));
        xt[4 * b + 288] = hadd2(xr[b][1], hmul2(pack(acc2[4 * b + 2], acc2[4 * b + 3]), gt[b][1]));
      }
      __syncwarp();
#pragma unroll
      for (int q5 = 0; q5 < 5; q5++) {
        const int q = q5 * 32 + lane, r = q / 9, ch = q - 9 * r;
        if (q < 144) *reinterpret_cast<uint4*>(ptrs.out + (size_t)(m * 128 + w8 * 16 + r) * (DM * 2) + j * 144 + ch * 16) = *reinterpret_cast<const uint4*>(smem + SM_XT + w8 * 2304 + q * 16);
      }
    }
    TS(11); TQ(58);
  }
  asm volatile("barrier.cluster.arrive.relaxed.aligned;\nbarrier.cluster.wait.aligned;" ::: "memory");
}

typedef CUresult (*EncodeFn)(CUtensorMap*, CUtensorMapDataType, cuuint32_t, void*, const cuuint64_t*, const cuuint64_t*, const cuuint32_t*, const cuuint32_t*, CUtensorMapInterleave, CUtensorMapSwizzle, CUtensorMapL2promotion, CUtensorMapFloatOOBfill);

void encode(EncodeFn fn, CUtensorMap* map, const void* ptr, int rank, const cuuint64_t* dims, const cuuint64_t* strides, const cuuint32_t* box, bool swz) {
  const cuuint32_t es[5] = {1, 1, 1, 1, 1};
  fn(map, CU_TENSOR_MAP_DATA_TYPE_BFLOAT16, rank, const_cast<void*>(ptr), dims, strides, box, es, CU_TENSOR_MAP_INTERLEAVE_NONE,
     swz ? CU_TENSOR_MAP_SWIZZLE_128B : CU_TENSOR_MAP_SWIZZLE_NONE, CU_TENSOR_MAP_L2_PROMOTION_L2_128B, CU_TENSOR_MAP_FLOAT_OOB_FILL_NONE);
}

}

extern "C" void kernel_launch(void* const* d_in, const int* in_sizes, int n_in, void* d_out, int out_size) {
  (void)in_sizes; (void)n_in; (void)out_size;
  static EncodeFn fn = nullptr;
  static Scratch* scratch = nullptr;
  if (!fn) {
    void* p = nullptr; cudaDriverEntryPointQueryResult q;
    cudaGetDriverEntryPoint("cuTensorMapEncodeTiled", &p, cudaEnableDefault, &q);
    fn = (EncodeFn)p;
    cudaGetSymbolAddress((void**)&scratch, g_scratch);
    cudaFuncSetAttribute(fused_kernel, cudaFuncAttributeMaxDynamicSharedMemorySize, SM_TOTAL + TEXTRA);
  }
  Maps mp;
  { cuuint64_t d[2] = {DM, S_LEN}, s[1] = {DM * 2}; cuuint32_t b[2] = {64, 128}; encode(fn, &mp.x, d_in[0], 2, d, s, b, true); }
  { cuuint64_t d[2] = {3 * DM, DM}, s[1] = {3 * DM * 2}; cuuint32_t b[2] = {64, 64}; encode(fn, &mp.qkv, d_in[1], 2, d, s, b, true); }
  { cuuint64_t d[2] = {FF, DM}, s[1] = {FF * 2}; cuuint32_t b[2] = {64, 64}; encode(fn, &mp.wg, d_in[4], 2, d, s, b, true); encode(fn, &mp.wu, d_in[5], 2, d, s, b, true); }
  { cuuint64_t d[5] = {DM, 2, 4, 4, FF / 32}, s[4] = {DM * 2, 8 * DM * 2, 2 * DM * 2, 32 * DM * 2}; cuuint32_t b[5] = {64, 2, 4, 4, 2}; encode(fn, &mp.wd, d_in[6], 5, d, s, b, true); }
  { cuuint64_t d[5] = {DM, 72, 2, 4, 8}, s[4] = {DM * 2, 8 * DM * 2, 2 * DM * 2, 72 * DM * 2}; cuuint32_t b[5] = {64, 2, 2, 4, 4}; encode(fn, &mp.woe, d_in[2], 5, d, s, b, true); }
  { cuuint64_t d[3] = {DM, 72, 8}, s[2] = {DM * 2, 72 * DM * 2}; cuuint32_t b[3] = {64, 16, 4}; encode(fn, &mp.woa, d_in[2], 3, d, s, b, true); }
  { cuuint64_t d[3] = {DM, 18, 32}, s[2] = {DM * 2, 18 * DM * 2}; cuuint32_t b[3] = {64, 2, 32}; encode(fn, &mp.wob, d_in[2], 3, d, s, b, true); }
  Ptrs pt = {(const uint8_t*)d_in[0], (const uint8_t*)d_in[1], (const uint8_t*)d_in[2], (const uint8_t*)d_in[4], (const uint8_t*)d_in[5], (const uint8_t*)d_in[6], (uint8_t*)d_out, scratch, 1};
  fused_kernel<<<128, 384, SM_TOTAL + TEXTRA>>>(mp, pt);
}
```
